```python
import torch

def _softmax(x, axis=-1):
    return torch.softmax(x, dim=axis)

def _gelu(x):
    return torch.nn.functional.gelu(x, approximate='tanh')

def _silu(x):
    return torch.nn.functional.silu(x)

def _sigmoid(x):
    return torch.sigmoid(x)

def _layernorm(x, axis=-1, eps=1e-05):
    m = x.mean(dim=axis, keepdim=True)
    v = x.var(dim=axis, keepdim=True, unbiased=False)
    return (x - m) / torch.sqrt(v + eps)

def _scatter_add(tgt, idx, src, axis=0):
    return tgt.clone().index_add_(axis, idx, src)

def _segment_sum(src, seg, n):
    out = torch.zeros((n,) + src.shape[1:], dtype=src.dtype)
    return out.index_add_(0, seg, src)

def _pad(x, pw):
    flat = tuple((v for pair in reversed(pw) for v in pair))
    return torch.nn.functional.pad(x, flat)
kernel_name = 'adaLN_cond__softmax_full_mha__mixer_gmlp__prompt'

def setup_inputs():

    _w = lambda a: (lambda t: t.to(torch.bfloat16) if t.is_floating_point() else t)(torch.as_tensor(a))

    def _A_setup():
        B, S, D = (1, 2048, 512)
        return {'x': _w((lambda *s: torch.randn(*s, dtype=torch.bfloat16) * 0.05)(B, S, D)), 'wqkv': _w((lambda *s: torch.randn(*s, dtype=torch.bfloat16) * 0.05)(D, 3 * D)), 'wo': _w((lambda *s: torch.randn(*s, dtype=torch.bfloat16) * 0.05)(D, D))}
    _A_in = _A_setup()

    def _B_setup():
        B, S, D, F = (1, 2048, 512, 1376)
        Fh = F // 2
        return {'x': _w((lambda *s: torch.randn(*s, dtype=torch.bfloat16) * 0.05)(B, S, D)), 'w_in': _w((lambda *s: torch.randn(*s, dtype=torch.bfloat16) * 0.4)(D, 2 * Fh)), 'w_sp': _w(0.01 * (lambda *s: torch.randn(*s, dtype=torch.bfloat16) * 0.4)(S, S)), 'b_sp': _w(1.0 + 0.01 * (lambda *s: torch.randn(*s, dtype=torch.bfloat16) * 0.05)(S)), 'w_out': _w((lambda *s: torch.randn(*s, dtype=torch.bfloat16) * 0.05)(Fh, D))}
    _B_in = _B_setup()
    return {'A_x': _A_in['x'], 'A_wqkv': _A_in['wqkv'], 'A_wo': _A_in['wo'], 'B_x': _B_in['x'], 'B_w_in': _B_in['w_in'], 'B_w_sp': _B_in['w_sp'], 'B_b_sp': _B_in['b_sp'], 'B_w_out': _B_in['w_out'], 'c': _w((lambda *s: torch.randn(*s, dtype=torch.bfloat16) * 0.1)(1, 512) * 8.0), 'w_mod': _w((lambda *s: torch.randn(*s, dtype=torch.bfloat16) * 0.1)(512, 6 * 512) * 512 ** (-0.5) * 8.0)}

def reference(A_x, A_wqkv, A_wo, B_x, B_w_in, B_w_sp, B_b_sp, B_w_out, c, w_mod):

    def _A_ref(x, wqkv, wo):
        B, S, D = x.shape
        H = 32
        Dh = D // H
        qkv = (lambda x, *d: x.permute(*d))((x @ wqkv).reshape(B, S, 3, H, Dh), 2, 0, 3, 1, 4)
        q, k, v = (qkv[0], qkv[1], qkv[2])
        scale = Dh ** (-0.5)
        scores = torch.einsum('bhqd,bhkd->bhqk', q, k) * scale
        p = _softmax(scores, axis=-1)
        o = torch.einsum('bhqk,bhkd->bhqd', p, v)
        return (lambda x, *d: x.permute(*d))(o, 0, 2, 1, 3).reshape(B, S, D) @ wo

    def _B_ref(x, w_in, w_sp, b_sp, w_out):
        B, S, D = x.shape
        F = w_in.shape[-1]
        Fh = F // 2
        z = _gelu(torch.einsum('bsd,df->bsf', x, w_in))
        z1 = z[..., :Fh].clone()
        z2 = _layernorm(z[..., Fh:], axis=-1)
        g = torch.einsum('ts,bsf->btf', w_sp, z2) + b_sp[None, :, None]
        return torch.einsum('bsf,fd->bsd', z1 * g, w_out)
    x = A_x
    mod = (_silu(c) @ w_mod).reshape(c.shape[0], 6, 1, -1)
    sa, ca, ga, sb, cb, gb = (mod[:, 0].clone(), mod[:, 1].clone(), mod[:, 2].clone(), mod[:, 3].clone(), mod[:, 4].clone(), mod[:, 5].clone())
    h = _layernorm(x, axis=-1) * (1 + ca) + sa
    x = x + ga * _A_ref(h, A_wqkv, A_wo)
    h = _layernorm(x, axis=-1) * (1 + cb) + sb
    x = x + gb * _B_ref(h, B_w_in, B_w_sp, B_b_sp, B_w_out)
    return x
```

```cpp
#include <cuda_runtime.h>
#include <cuda_bf16.h>
#include <cuda.h>
#include <cstdint>

typedef __nv_bfloat16 bf16;
constexpr int S_LEN = 2048;

struct Scratch {
  alignas(1024) bf16  g_mod[3072];
  alignas(1024) bf16  g_qkv[96 * 2048 * 16];
  alignas(1024) float g_nrm[96 * 128];
  alignas(1024) bf16  g_o[2048 * 512];
  alignas(1024) bf16  g_x1[2048 * 512];
  alignas(1024) float2 g_st2[2048 * 8];
  alignas(1024) float2 g_st3[2048 * 8];
  alignas(1024) unsigned long long g_modx[512];
  alignas(1024) bf16  g_wt[8 * 176 * 512];
  alignas(1024) float2 g_cs[4 * 8 * 176];
  alignas(1024) unsigned long long g_st1[2048];
  alignas(1024) uint32_t g_flag[1280];
  alignas(1024) bf16  g_z2t[688 * 2048];
  alignas(1024) bf16  g_u[2048 * 512];
  alignas(1024) bf16  g_ul[32 * 24 * 512];
};
__device__ Scratch g_scratch;

#define TS(k, i)
#define TC(i)
#define TM(i)
#define TA(i)
#define WG_FENCE()  asm volatile("wgmma.fence.sync.aligned;" ::: "memory")
#define WG_COMMIT() asm volatile("wgmma.commit_group.sync.aligned;" ::: "memory")
#define WG_WAIT(n)  asm volatile("wgmma.wait_group.sync.aligned %0;" :: "n"(n) : "memory")
#define DEVI __device__ __forceinline__
DEVI void pdl_wait()    { asm volatile("griddepcontrol.wait;" ::: "memory"); }
DEVI void pdl_trigger() { asm volatile("griddepcontrol.launch_dependents;" ::: "memory"); }
DEVI uint32_t smem_u32(const void* p) { return (uint32_t)__cvta_generic_to_shared(p); }
DEVI void mbar_init(uint32_t bar, int cnt) { asm volatile("mbarrier.init.shared::cta.b64 [%0], %1;" :: "r"(bar), "r"(cnt)); }
DEVI void mbar_expect(uint32_t bar, int bytes) { asm volatile("mbarrier.arrive.expect_tx.shared::cta.b64 _, [%0], %1;" :: "r"(bar), "r"(bytes) : "memory"); }
DEVI void mbar_wait(uint32_t bar, int parity) {
  asm volatile("{\n.reg .pred p;\n.reg .u32 c;\nmov.u32 c, 0;\n"
               "WL%=:\nmbarrier.try_wait.parity.shared::cta.b64 p, [%0], %1;\n@p bra DN%=;\n"
               "add.u32 c, c, 1;\nsetp.lt.u32 p, c, 0x400000;\n@p bra WL%=;\ntrap;\nDN%=:\n}"
               :: "r"(bar), "r"(parity) : "memory");
}
DEVI uint32_t mbar_test(uint32_t bar, int parity) {
  uint32_t r;
  asm volatile("{\n.reg .pred p;\nmbarrier.test_wait.parity.shared::cta.b64 p, [%1], %2;\nselp.u32 %0, 1, 0, p;\n}" : "=r"(r) : "r"(bar), "r"(parity) : "memory");
  return r;
}
DEVI void mbar_arrive_rank(uint32_t bar, uint32_t rank) {
  asm volatile("{\n.reg .b32 ra;\nmapa.shared::cluster.u32 ra, %0, %1;\n"
               "mbarrier.arrive.shared::cluster.b64 _, [ra];\n}" :: "r"(bar), "r"(rank) : "memory");
}
DEVI void fence_bar_init() { asm volatile("fence.mbarrier_init.release.cluster;" ::: "memory"); }
DEVI void cluster_sync() { asm volatile("barrier.cluster.arrive.relaxed.aligned;\nbarrier.cluster.wait.aligned;" ::: "memory"); }
DEVI void cluster_arrive() { asm volatile("barrier.cluster.arrive.relaxed.aligned;" ::: "memory"); }
DEVI void cluster_wait() { asm volatile("barrier.cluster.wait.aligned;" ::: "memory"); }
DEVI uint32_t cluster_rank() { uint32_t r; asm("mov.u32 %0, %%cluster_ctarank;" : "=r"(r)); return r; }
DEVI void bar_sync(int id, int n) { asm volatile("bar.sync %0, %1;" :: "r"(id), "r"(n) : "memory"); }
DEVI void bar_arrive(int id, int n) { asm volatile("bar.arrive %0, %1;" :: "r"(id), "r"(n) : "memory"); }
DEVI void tma2d(uint32_t dst, const CUtensorMap* tm, uint32_t bar, int c0, int c1) {
  asm volatile("cp.async.bulk.tensor.2d.shared::cluster.global.mbarrier::complete_tx::bytes [%0], [%1, {%3, %4}], [%2];"
               :: "r"(dst), "l"(tm), "r"(bar), "r"(c0), "r"(c1) : "memory");
}
DEVI void tma2d_mc(uint32_t dst, const CUtensorMap* tm, uint32_t bar, int c0, int c1) {
  asm volatile("cp.async.bulk.tensor.2d.shared::cluster.global.mbarrier::complete_tx::bytes.multicast::cluster [%0], [%1, {%3, %4}], [%2], %5;"
               :: "r"(dst), "l"(tm), "r"(bar), "r"(c0), "r"(c1), "h"((uint16_t)3) : "memory");
}
DEVI void bulk_g2s(uint32_t dst, const void* src, int bytes, uint32_t bar) {
  asm volatile("cp.async.bulk.shared::cluster.global.mbarrier::complete_tx::bytes [%0], [%1], %2, [%3];"
               :: "r"(dst), "l"(src), "r"(bytes), "r"(bar) : "memory");
}
DEVI void bulk_g2s_mc(uint32_t dst, const void* src, int bytes, uint32_t bar) {
  asm volatile("cp.async.bulk.shared::cluster.global.mbarrier::complete_tx::bytes.multicast::cluster [%0], [%1], %2, [%3], %4;"
               :: "r"(dst), "l"(src), "r"(bytes), "r"(bar), "h"((uint16_t)3) : "memory");
}
DEVI void l2_prefetch(const void* p, int bytes) { asm volatile("cp.async.bulk.prefetch.L2.global [%0], %1;" :: "l"(p), "r"(bytes) : "memory"); }
DEVI void tmap_prefetch(const CUtensorMap* tm) { asm volatile("prefetch.tensormap [%0];" :: "l"(tm) : "memory"); }
DEVI void ldsm4(uint32_t (&r)[4], uint32_t a) {
  asm volatile("ldmatrix.sync.aligned.m8n8.x4.shared.b16 {%0,%1,%2,%3}, [%4];" : "=r"(r[0]), "=r"(r[1]), "=r"(r[2]), "=r"(r[3]) : "r"(a) : "memory");
}
DEVI void stsm4(uint32_t a, uint32_t r0, uint32_t r1, uint32_t r2, uint32_t r3) {
  asm volatile("stmatrix.sync.aligned.m8n8.x4.shared.b16 [%0], {%1,%2,%3,%4};" :: "r"(a), "r"(r0), "r"(r1), "r"(r2), "r"(r3) : "memory");
}
DEVI void stsm4t(uint32_t a, uint32_t r0, uint32_t r1, uint32_t r2, uint32_t r3) {
  asm volatile("stmatrix.sync.aligned.m8n8.x4.trans.shared.b16 [%0], {%1,%2,%3,%4};" :: "r"(a), "r"(r0), "r"(r1), "r"(r2), "r"(r3) : "memory");
}
DEVI void stsm2(uint32_t a, uint32_t r0, uint32_t r1) {
  asm volatile("stmatrix.sync.aligned.m8n8.x2.shared.b16 [%0], {%1,%2};" :: "r"(a), "r"(r0), "r"(r1) : "memory");
}
DEVI void stsm2t(uint32_t a, uint32_t r0, uint32_t r1) {
  asm volatile("stmatrix.sync.aligned.m8n8.x2.trans.shared.b16 [%0], {%1,%2};" :: "r"(a), "r"(r0), "r"(r1) : "memory");
}
DEVI uint4 lds128(uint32_t a) { uint4 v; asm volatile("ld.shared.v4.u32 {%0,%1,%2,%3}, [%4];" : "=r"(v.x), "=r"(v.y), "=r"(v.z), "=r"(v.w) : "r"(a) : "memory"); return v; }
DEVI void sts128(uint32_t a, uint4 v) { asm volatile("st.shared.v4.u32 [%0], {%1,%2,%3,%4};" :: "r"(a), "r"(v.x), "r"(v.y), "r"(v.z), "r"(v.w) : "memory"); }
DEVI void mma16816(float (&c)[4], const uint32_t (&a)[4], uint32_t b0, uint32_t b1) {
  asm("mma.sync.aligned.m16n8k16.row.col.f32.bf16.bf16.f32 {%0,%1,%2,%3}, {%4,%5,%6,%7}, {%8,%9}, {%0,%1,%2,%3};"
               : "+f"(c[0]), "+f"(c[1]), "+f"(c[2]), "+f"(c[3]) : "r"(a[0]), "r"(a[1]), "r"(a[2]), "r"(a[3]), "r"(b0), "r"(b1));
}
DEVI float ex2(float x) { float y; asm("ex2.approx.ftz.f32 %0, %1;" : "=f"(y) : "f"(x)); return y; }
DEVI float tanh_fast(float x) { float y; asm("tanh.approx.f32 %0, %1;" : "=f"(y) : "f"(x)); return y; }
DEVI uint32_t pack(float lo, float hi) { uint32_t r; asm("cvt.rn.bf16x2.f32 %0, %1, %2;" : "=r"(r) : "f"(hi), "f"(lo)); return r; }
DEVI uint32_t hfma2(uint32_t a, uint32_t b, uint32_t c) { uint32_t r; asm("fma.rn.bf16x2 %0, %1, %2, %3;" : "=r"(r) : "r"(a), "r"(b), "r"(c)); return r; }
DEVI uint32_t hadd2(uint32_t a, uint32_t b) { uint32_t r; asm("add.rn.bf16x2 %0, %1, %2;" : "=r"(r) : "r"(a), "r"(b)); return r; }
DEVI uint32_t hmul2(uint32_t a, uint32_t b) { uint32_t r; asm("mul.rn.bf16x2 %0, %1, %2;" : "=r"(r) : "r"(a), "r"(b)); return r; }
DEVI float blo(uint32_t v) { return __uint_as_float(v << 16); }
DEVI float bhi(uint32_t v) { return __uint_as_float(v & 0xFFFF0000u); }
DEVI float rbf(float x) { return __bfloat162float(__float2bfloat16_rn(x)); }
template<int N> DEVI void fence_regs(float (&d)[N]) {
  #pragma unroll
  for (int i = 0; i < N; i++) asm volatile("" : "+f"(d[i]) :: "memory");
}
DEVI uint32_t daddr(uint32_t a) { return (a & 0x3FFFF) >> 4; }
DEVI uint64_t mkdesc(uint32_t hi, uint32_t lo) { return ((uint64_t)hi << 32) | lo; }
constexpr uint32_t DHI128 = (1u << 30) | (1024 >> 4);
constexpr uint32_t DHI32  = (3u << 30) | (256 >> 4);

template<int TB> __device__ __forceinline__ void wg_n192_rs_a(float (&d)[96], const uint32_t (&a)[4], uint64_t db) {
  asm volatile("{\n.reg .pred p;\nsetp.eq.b32 p, 0, 0;\n"
    "wgmma.mma_async.sync.aligned.m64n192k16.f32.bf16.bf16 {%0, %1, %2, %3, %4, %5, %6, %7, %8, %9, %10, %11, %12, %13, %14, %15, "
    "%16, %17, %18, %19, %20, %21, %22, %23, %24, %25, %26, %27, %28, %29, %30, %31, "
    "%32, %33, %34, %35, %36, %37, %38, %39, %40, %41, %42, %43, %44, %45, %46, %47, "
    "%48, %49, %50, %51, %52, %53, %54, %55, %56, %57, %58, %59, %60, %61, %62, %63, "
    "%64, %65, %66, %67, %68, %69, %70, %71, %72, %73, %74, %75, %76, %77, %78, %79, "
    "%80, %81, %82, %83, %84, %85, %86, %87, %88, %89, %90, %91, %92, %93, %94, %95}, {%96, %97, %98, %99}, %100, p, 1, 1, %101;\n}\n"
    : "+f"(d[0]), "+f"(d[1]), "+f"(d[2]), "+f"(d[3]), "+f"(d[4]), "+f"(d[5]), "+f"(d[6]), "+f"(d[7]),
      "+f"(d[8]), "+f"(d[9]), "+f"(d[10]), "+f"(d[11]), "+f"(d[12]), "+f"(d[13]), "+f"(d[14]), "+f"(d[15]),
      "+f"(d[16]), "+f"(d[17]), "+f"(d[18]), "+f"(d[19]), "+f"(d[20]), "+f"(d[21]), "+f"(d[22]), "+f"(d[23]),
      "+f"(d[24]), "+f"(d[25]), "+f"(d[26]), "+f"(d[27]), "+f"(d[28]), "+f"(d[29]), "+f"(d[30]), "+f"(d[31]),
      "+f"(d[32]), "+f"(d[33]), "+f"(d[34]), "+f"(d[35]), "+f"(d[36]), "+f"(d[37]), "+f"(d[38]), "+f"(d[39]),
      "+f"(d[40]), "+f"(d[41]), "+f"(d[42]), "+f"(d[43]), "+f"(d[44]), "+f"(d[45]), "+f"(d[46]), "+f"(d[47]),
      "+f"(d[48]), "+f"(d[49]), "+f"(d[50]), "+f"(d[51]), "+f"(d[52]), "+f"(d[53]), "+f"(d[54]), "+f"(d[55]),
      "+f"(d[56]), "+f"(d[57]), "+f"(d[58]), "+f"(d[59]), "+f"(d[60]), "+f"(d[61]), "+f"(d[62]), "+f"(d[63]),
      "+f"(d[64]), "+f"(d[65]), "+f"(d[66]), "+f"(d[67]), "+f"(d[68]), "+f"(d[69]), "+f"(d[70]), "+f"(d[71]),
      "+f"(d[72]), "+f"(d[73]), "+f"(d[74]), "+f"(d[75]), "+f"(d[76]), "+f"(d[77]), "+f"(d[78]), "+f"(d[79]),
      "+f"(d[80]), "+f"(d[81]), "+f"(d[82]), "+f"(d[83]), "+f"(d[84]), "+f"(d[85]), "+f"(d[86]), "+f"(d[87]),
      "+f"(d[88]), "+f"(d[89]), "+f"(d[90]), "+f"(d[91]), "+f"(d[92]), "+f"(d[93]), "+f"(d[94]), "+f"(d[95])
    : "r"(a[0]), "r"(a[1]), "r"(a[2]), "r"(a[3]), "l"(db), "n"(TB));
}
template<int TB> __device__ __forceinline__ void wg_n192_rs_z(float (&d)[96], const uint32_t (&a)[4], uint64_t db) {
  asm volatile("{\n.reg .pred p;\nsetp.ne.b32 p, 0, 0;\n"
    "wgmma.mma_async.sync.aligned.m64n192k16.f32.bf16.bf16 {%0, %1, %2, %3, %4, %5, %6, %7, %8, %9, %10, %11, %12, %13, %14, %15, "
    "%16, %17, %18, %19, %20, %21, %22, %23, %24, %25, %26, %27, %28, %29, %30, %31, "
    "%32, %33, %34, %35, %36, %37, %38, %39, %40, %41, %42, %43, %44, %45, %46, %47, "
    "%48, %49, %50, %51, %52, %53, %54, %55, %56, %57, %58, %59, %60, %61, %62, %63, "
    "%64, %65, %66, %67, %68, %69, %70, %71, %72, %73, %74, %75, %76, %77, %78, %79, "
    "%80, %81, %82, %83, %84, %85, %86, %87, %88, %89, %90, %91, %92, %93, %94, %95}, {%96, %97, %98, %99}, %100, p, 1, 1, %101;\n}\n"
    : "=f"(d[0]), "=f"(d[1]), "=f"(d[2]), "=f"(d[3]), "=f"(d[4]), "=f"(d[5]), "=f"(d[6]), "=f"(d[7]),
      "=f"(d[8]), "=f"(d[9]), "=f"(d[10]), "=f"(d[11]), "=f"(d[12]), "=f"(d[13]), "=f"(d[14]), "=f"(d[15]),
      "=f"(d[16]), "=f"(d[17]), "=f"(d[18]), "=f"(d[19]), "=f"(d[20]), "=f"(d[21]), "=f"(d[22]), "=f"(d[23]),
      "=f"(d[24]), "=f"(d[25]), "=f"(d[26]), "=f"(d[27]), "=f"(d[28]), "=f"(d[29]), "=f"(d[30]), "=f"(d[31]),
      "=f"(d[32]), "=f"(d[33]), "=f"(d[34]), "=f"(d[35]), "=f"(d[36]), "=f"(d[37]), "=f"(d[38]), "=f"(d[39]),
      "=f"(d[40]), "=f"(d[41]), "=f"(d[42]), "=f"(d[43]), "=f"(d[44]), "=f"(d[45]), "=f"(d[46]), "=f"(d[47]),
      "=f"(d[48]), "=f"(d[49]), "=f"(d[50]), "=f"(d[51]), "=f"(d[52]), "=f"(d[53]), "=f"(d[54]), "=f"(d[55]),
      "=f"(d[56]), "=f"(d[57]), "=f"(d[58]), "=f"(d[59]), "=f"(d[60]), "=f"(d[61]), "=f"(d[62]), "=f"(d[63]),
      "=f"(d[64]), "=f"(d[65]), "=f"(d[66]), "=f"(d[67]), "=f"(d[68]), "=f"(d[69]), "=f"(d[70]), "=f"(d[71]),
      "=f"(d[72]), "=f"(d[73]), "=f"(d[74]), "=f"(d[75]), "=f"(d[76]), "=f"(d[77]), "=f"(d[78]), "=f"(d[79]),
      "=f"(d[80]), "=f"(d[81]), "=f"(d[82]), "=f"(d[83]), "=f"(d[84]), "=f"(d[85]), "=f"(d[86]), "=f"(d[87]),
      "=f"(d[88]), "=f"(d[89]), "=f"(d[90]), "=f"(d[91]), "=f"(d[92]), "=f"(d[93]), "=f"(d[94]), "=f"(d[95])
    : "r"(a[0]), "r"(a[1]), "r"(a[2]), "r"(a[3]), "l"(db), "n"(TB));
}
template<int TB> __device__ __forceinline__ void wg_n24_rs_a(float (&d)[12], const uint32_t (&a)[4], uint64_t db) {
  asm volatile("{\n.reg .pred p;\nsetp.eq.b32 p, 0, 0;\n"
    "wgmma.mma_async.sync.aligned.m64n24k16.f32.bf16.bf16 {%0, %1, %2, %3, %4, %5, %6, %7, %8, %9, %10, %11}, {%12, %13, %14, %15}, %16, p, 1, 1, %17;\n}\n"
    : "+f"(d[0]), "+f"(d[1]), "+f"(d[2]), "+f"(d[3]), "+f"(d[4]), "+f"(d[5]), "+f"(d[6]), "+f"(d[7]),
      "+f"(d[8]), "+f"(d[9]), "+f"(d[10]), "+f"(d[11])
    : "r"(a[0]), "r"(a[1]), "r"(a[2]), "r"(a[3]), "l"(db), "n"(TB));
}
template<int TB> __device__ __forceinline__ void wg_n64_rs_z(float (&d)[32], const uint32_t (&a)[4], uint64_t db) {
  asm volatile("{\n.reg .pred p;\nsetp.ne.b32 p, 0, 0;\n"
    "wgmma.mma_async.sync.aligned.m64n64k16.f32.bf16.bf16 {%0, %1, %2, %3, %4, %5, %6, %7, %8, %9, %10, %11, %12, %13, %14, %15, "
    "%16, %17, %18, %19, %20, %21, %22, %23, %24, %25, %26, %27, %28, %29, %30, %31}, {%32, %33, %34, %35}, %36, p, 1, 1, %37;\n}\n"
    : "=f"(d[0]), "=f"(d[1]), "=f"(d[2]), "=f"(d[3]), "=f"(d[4]), "=f"(d[5]), "=f"(d[6]), "=f"(d[7]),
      "=f"(d[8]), "=f"(d[9]), "=f"(d[10]), "=f"(d[11]), "=f"(d[12]), "=f"(d[13]), "=f"(d[14]), "=f"(d[15]),
      "=f"(d[16]), "=f"(d[17]), "=f"(d[18]), "=f"(d[19]), "=f"(d[20]), "=f"(d[21]), "=f"(d[22]), "=f"(d[23]),
      "=f"(d[24]), "=f"(d[25]), "=f"(d[26]), "=f"(d[27]), "=f"(d[28]), "=f"(d[29]), "=f"(d[30]), "=f"(d[31])
    : "r"(a[0]), "r"(a[1]), "r"(a[2]), "r"(a[3]), "l"(db), "n"(TB));
}
template<int TA, int TB> __device__ __forceinline__ void wg_n64_ss_a(float (&d)[32], uint64_t da, uint64_t db) {
  asm volatile("{\n.reg .pred p;\nsetp.eq.b32 p, 0, 0;\n"
    "wgmma.mma_async.sync.aligned.m64n64k16.f32.bf16.bf16 {%0, %1, %2, %3, %4, %5, %6, %7, %8, %9, %10, %11, %12, %13, %14, %15, "
    "%16, %17, %18, %19, %20, %21, %22, %23, %24, %25, %26, %27, %28, %29, %30, %31}, %32, %33, p, 1, 1, %34, %35;\n}\n"
    : "+f"(d[0]), "+f"(d[1]), "+f"(d[2]), "+f"(d[3]), "+f"(d[4]), "+f"(d[5]), "+f"(d[6]), "+f"(d[7]),
      "+f"(d[8]), "+f"(d[9]), "+f"(d[10]), "+f"(d[11]), "+f"(d[12]), "+f"(d[13]), "+f"(d[14]), "+f"(d[15]),
      "+f"(d[16]), "+f"(d[17]), "+f"(d[18]), "+f"(d[19]), "+f"(d[20]), "+f"(d[21]), "+f"(d[22]), "+f"(d[23]),
      "+f"(d[24]), "+f"(d[25]), "+f"(d[26]), "+f"(d[27]), "+f"(d[28]), "+f"(d[29]), "+f"(d[30]), "+f"(d[31])
    : "l"(da), "l"(db), "n"(TA), "n"(TB));
}
template<int TA, int TB> __device__ __forceinline__ void wg_n88_ss_a(float (&d)[44], uint64_t da, uint64_t db) {
  asm volatile("{\n.reg .pred p;\nsetp.eq.b32 p, 0, 0;\n"
    "wgmma.mma_async.sync.aligned.m64n88k16.f32.bf16.bf16 {%0, %1, %2, %3, %4, %5, %6, %7, %8, %9, %10, %11, %12, %13, %14, %15, "
    "%16, %17, %18, %19, %20, %21, %22, %23, %24, %25, %26, %27, %28, %29, %30, %31, "
    "%32, %33, %34, %35, %36, %37, %38, %39, %40, %41, %42, %43}, %44, %45, p, 1, 1, %46, %47;\n}\n"
    : "+f"(d[0]), "+f"(d[1]), "+f"(d[2]), "+f"(d[3]), "+f"(d[4]), "+f"(d[5]), "+f"(d[6]), "+f"(d[7]),
      "+f"(d[8]), "+f"(d[9]), "+f"(d[10]), "+f"(d[11]), "+f"(d[12]), "+f"(d[13]), "+f"(d[14]), "+f"(d[15]),
      "+f"(d[16]), "+f"(d[17]), "+f"(d[18]), "+f"(d[19]), "+f"(d[20]), "+f"(d[21]), "+f"(d[22]), "+f"(d[23]),
      "+f"(d[24]), "+f"(d[25]), "+f"(d[26]), "+f"(d[27]), "+f"(d[28]), "+f"(d[29]), "+f"(d[30]), "+f"(d[31]),
      "+f"(d[32]), "+f"(d[33]), "+f"(d[34]), "+f"(d[35]), "+f"(d[36]), "+f"(d[37]), "+f"(d[38]), "+f"(d[39]),
      "+f"(d[40]), "+f"(d[41]), "+f"(d[42]), "+f"(d[43])
    : "l"(da), "l"(db), "n"(TA), "n"(TB));
}

DEVI void ln_params(float sum, float sq, float inv_n, uint32_t& negm2, uint32_t& sd2, float& rs) {
  float mean = sum * inv_n;
  float var = fmaxf(sq * inv_n - mean * mean, 0.f);
  float sd;
  asm("sqrt.approx.f32 %0, %1;" : "=f"(sd) : "f"(rbf(rbf(var) + 1e-5f)));
  sd = rbf(sd);
  negm2 = pack(-mean, -mean);
  sd2 = pack(sd, sd);
  asm("rcp.approx.f32 %0, %1;" : "=f"(rs) : "f"(sd));
}

constexpr int T1_E = 1, T1_A = 0, T1_B = 131072, T1_NB = 4, T1_GS = T1_B + T1_NB * 24576, T1_BAR = T1_GS + 2048, T1_RED = T1_BAR + 128, T1_SMEM = T1_RED + 256;
DEVI float silu_bf(bf16 c) { const float v = __bfloat162float(c); return rbf(v / (1.0f + __expf(-v))); }
DEVI void fma8(float (&a)[8], float s, uint4 w) {
  a[0] = fmaf(s, blo(w.x), a[0]); a[1] = fmaf(s, bhi(w.x), a[1]); a[2] = fmaf(s, blo(w.y), a[2]); a[3] = fmaf(s, bhi(w.y), a[3]);
  a[4] = fmaf(s, blo(w.z), a[4]); a[5] = fmaf(s, bhi(w.z), a[5]); a[6] = fmaf(s, blo(w.w), a[6]); a[7] = fmaf(s, bhi(w.w), a[7]);
}

__global__ void __cluster_dims__(2, 1, 1) __launch_bounds__(384, 1)
k1_qkv(const __grid_constant__ CUtensorMap tmA, const __grid_constant__ CUtensorMap tmB, Scratch* __restrict__ S,
       const bf16* __restrict__ x, const bf16* __restrict__ c, const bf16* __restrict__ wmod, const bf16* __restrict__ wqkv) {
  extern __shared__ __align__(1024) uint8_t smem[];
  TS(1, 0);
  const uint32_t sb = smem_u32(smem);
  const uint32_t barA = sb + T1_BAR, barF = barA + 64, barE = barF + 32;
  const int tid = threadIdx.x, lane = tid & 31, warp = tid >> 5;
  const uint32_t rank = blockIdx.x & 1;
  const int ct = (blockIdx.x >> 1) & 7, rt = ((blockIdx.x >> 4) << 1) | rank;
  const int n0 = ct * 192;
  uint4 w0, w1, xr[4]; bf16 c0v, c1v;
  const int srw = rt * 128 + ct * 16 + warp * 2 + (lane >> 4);
  if (warp < 8) {
    w0 = __ldg((const uint4*)(wmod + (size_t)tid * 3072 + blockIdx.x * 8));
    w1 = __ldg((const uint4*)(wmod + (size_t)(tid + 256) * 3072 + blockIdx.x * 8));
    c0v = c[tid]; c1v = c[tid + 256];
    #pragma unroll
    for (int i = 0; i < 4; i++) xr[i] = __ldg((const uint4*)(x + (size_t)srw * 512) + i * 16 + (lane & 15));
  }
  if (tid == 0) {
    for (int i = 0; i < 8; i++) mbar_init(barA + 8 * i, 1);
    for (int i = 0; i < T1_NB; i++) { mbar_init(barF + 8 * i, 1); mbar_init(barE + 8 * i, 16); }
    fence_bar_init();
    for (int i = 0; i < 8; i++) mbar_expect(barA + 8 * i, 16384);
    for (int i = 0; i < T1_NB; i++) mbar_expect(barF + 8 * i, 24576);
  }
  pdl_trigger();
  __syncwarp();
  cluster_arrive();
  TS(1, 7);
  if (warp >= 8) {
    asm volatile("setmaxnreg.dec.sync.aligned.u32 40;");
    if (warp > 8) return;
    cluster_wait();
    auto ldA = [&](int i) { tma2d(sb + T1_A + i * 16384, &tmA, barA + 8 * i, i * 64, rt * 128); };
    auto ldB = [&](int s) { if ((s & 1) == rank) for (int j = 0; j < 3; j++) tma2d_mc(sb + T1_B + (s % T1_NB) * 24576 + j * 8192, &tmB, barF + 8 * (s % T1_NB), n0 + j * 64, s * 64); };
    if (lane == 0) { ldA(0); ldB(0); ldA(1); }
    if (tid == 257) l2_prefetch((const uint8_t*)wqkv + T1_E * 196608 + blockIdx.x * (8 - T1_E) * 1536, (8 - T1_E) * 1536);
    bar_sync(1, 288);
    if (lane == 0) {
      ldB(1); for (int s = 2; s < T1_NB; s++) { ldA(s); ldB(s); }
      for (int s = T1_NB; s < 8; s++) {
        ldA(s);
        mbar_wait(barE + 8 * (s % T1_NB), 0); mbar_expect(barF + 8 * (s % T1_NB), 24576);
        ldB(s);
      }
    }
    return;
  }
  asm volatile("setmaxnreg.inc.sync.aligned.u32 232;");
  {
    float a[8];
    #pragma unroll
    for (int j = 0; j < 8; j++) a[j] = 0.f;
    fma8(a, silu_bf(c0v), w0); fma8(a, silu_bf(c1v), w1);
    #pragma unroll
    for (int j = 0; j < 4; j++) { const bool up = lane & 16; const float snd = up ? a[j] : a[j + 4], kp = up ? a[j + 4] : a[j]; a[j] = kp + __shfl_xor_sync(~0u, snd, 16); }
    #pragma unroll
    for (int j = 0; j < 2; j++) { const bool up = lane & 8; const float snd = up ? a[j] : a[j + 2], kp = up ? a[j + 2] : a[j]; a[j] = kp + __shfl_xor_sync(~0u, snd, 8); }
    { const bool up = lane & 4; const float snd = up ? a[0] : a[1], kp = up ? a[1] : a[0]; a[0] = kp + __shfl_xor_sync(~0u, snd, 4); }
    a[0] += __shfl_xor_sync(~0u, a[0], 2); a[0] += __shfl_xor_sync(~0u, a[0], 1);
    float* red = (float*)(smem + T1_RED);
    if ((lane & 3) == 0) red[warp * 8 + (lane >> 2)] = a[0];
    TS(1, 5);
    float s = 0.f, q = 0.f;
    #pragma unroll
    for (int i = 0; i < 4; i++) {
      const uint32_t w[4] = {xr[i].x, xr[i].y, xr[i].z, xr[i].w};
      #pragma unroll
      for (int j = 0; j < 4; j++) { const float u = blo(w[j]), v = bhi(w[j]); s += u + v; q = fmaf(u, u, fmaf(v, v, q)); }
    }
    #pragma unroll
    for (int o = 1; o < 16; o <<= 1) { s += __shfl_xor_sync(~0u, s, o); q += __shfl_xor_sync(~0u, q, o); }
    if ((lane & 15) == 0) {
      uint32_t nm, sd; float rs;
      ln_params(s, q, 1.f / 512, nm, sd, rs);
      const unsigned long long v = ((unsigned long long)(__float_as_uint(rs) | 0x80000000u) << 32) | __byte_perm(nm, sd, 0x5410);
      asm volatile("st.relaxed.gpu.global.u64 [%0], %1;" :: "l"(S->g_st1 + srw), "l"(v) : "memory");
    }
    TS(1, 6);
    bar_sync(2, 256);
    if (tid < 4) {
      float s0 = 0.f, s1 = 0.f;
      #pragma unroll
      for (int w = 0; w < 8; w++) { s0 += red[w * 8 + 2 * tid]; s1 += red[w * 8 + 2 * tid + 1]; }
      const unsigned long long v = (1ull << 32) | pack(s0, s1);
      asm volatile("st.relaxed.gpu.global.u64 [%0], %1;" :: "l"(S->g_modx + blockIdx.x * 4 + tid), "l"(v) : "memory");
    }
  }
  const int g = lane >> 2, t = lane & 3;
  const int wrow = warp * 16;
  const uint32_t aaddr = sb + T1_A + (wrow + (lane & 15)) * 128;
  const uint32_t asw = lane & 7, ahi = lane >> 4;
  uint32_t nm0, nm1, sd0, sd1; float rs0, rs1;
  TS(1, 1);
  {
    const int e = tid >> 1, hi = tid & 1;
    const unsigned long long* mp = S->g_modx + (e >> 2) * 8 + (e & 3) + hi * 4;
    const unsigned long long* sp = S->g_st1 + rt * 128 + wrow + g;
    unsigned long long vs, vc, v0, v1; int guard = 0;
    do {
      asm volatile("ld.relaxed.gpu.global.u64 %0, [%1];" : "=l"(vs) : "l"(mp) : "memory");
      asm volatile("ld.relaxed.gpu.global.u64 %0, [%1];" : "=l"(vc) : "l"(mp + 256) : "memory");
      asm volatile("ld.relaxed.gpu.global.u64 %0, [%1];" : "=l"(v0) : "l"(sp) : "memory");
      asm volatile("ld.relaxed.gpu.global.u64 %0, [%1];" : "=l"(v1) : "l"(sp + 8) : "memory");
    } while (((vs >> 32) == 0 || (vc >> 32) == 0 || (long long)(v0 & v1) >= 0) && ++guard < (1 << 20));
    uint32_t* gsp = (uint32_t*)(smem + T1_GS);
    gsp[(e >> 3) * 16 + (e & 3) * 4 + ((e >> 2) & 1) * 2 + hi] = hadd2((uint32_t)vc, 0x3F803F80u);
    gsp[256 + tid] = (uint32_t)vs;
    nm0 = __byte_perm((uint32_t)v0, 0, 0x1010); sd0 = __byte_perm((uint32_t)v0, 0, 0x3232); rs0 = __uint_as_float((uint32_t)(v0 >> 32) & 0x7FFFFFFFu);
    nm1 = __byte_perm((uint32_t)v1, 0, 0x1010); sd1 = __byte_perm((uint32_t)v1, 0, 0x3232); rs1 = __uint_as_float((uint32_t)(v1 >> 32) & 0x7FFFFFFFu);
  }
  bar_sync(1, 288);
  TS(1, 2);
  float acc[96];
  uint4 gr[16];
  #pragma unroll
  for (int i = 0; i < 16; i++) gr[i] = lds128(sb + T1_GS + i * 64 + t * 16);
  uint32_t e[3][4], a[4]; uint2 sv;
  const uint32_t bd0 = daddr(sb + T1_B) | ((8192 >> 4) << 16);
  auto fetch = [&](int ks) {
    if ((ks & 3) == 0) mbar_wait(barA + 8 * (ks >> 2), 0);
    ldsm4(a, aaddr + (ks >> 2) * 16384 + ((((ks & 3) * 2 + ahi) ^ asw) << 4));
    asm volatile("ld.shared.v2.u32 {%0,%1}, [%2];" : "=r"(sv.x), "=r"(sv.y) : "r"(sb + T1_GS + 1024 + ks * 32 + t * 8) : "memory");
  };
  fetch(0);
  #pragma unroll
  for (int ks = 0; ks < 32; ks++) {
    const int kc = ks >> 2, kk = ks & 3, sl = kc % T1_NB;
    uint32_t (&ee)[4] = e[ks % 3];
    const uint32_t g0 = (ks & 1) ? gr[ks >> 1].z : gr[ks >> 1].x, g1 = (ks & 1) ? gr[ks >> 1].w : gr[ks >> 1].y;
    ee[0] = hfma2(hadd2(a[0], nm0), g0, hmul2(sv.x, sd0));
    ee[1] = hfma2(hadd2(a[1], nm1), g0, hmul2(sv.x, sd1));
    ee[2] = hfma2(hadd2(a[2], nm0), g1, hmul2(sv.y, sd0));
    ee[3] = hfma2(hadd2(a[3], nm1), g1, hmul2(sv.y, sd1));
    if (ks < 31) fetch(ks + 1);
    if (kk == 0) mbar_wait(barF + 8 * sl, kc / T1_NB);
    WG_FENCE();
    const uint64_t db = mkdesc(DHI128, bd0 + (sl * 24576 + kk * 2048) / 16);
    if (ks == 0) wg_n192_rs_z<1>(acc, ee, db); else wg_n192_rs_a<1>(acc, ee, db);
    WG_COMMIT();
    WG_WAIT(1);
    if (kk == 0 && kc >= 1 && kc - 1 + T1_NB < 8 && lane < 2) mbar_arrive_rank(barE + 8 * (kc - 1), lane);
  }
  WG_WAIT(0);
  fence_regs(acc);
  TS(1, 3);
  const int row0 = rt * 128 + wrow;
  const uint32_t stg = sb + T1_A + wrow * 128;
  const int srow = ((lane >> 3) & 1) * 8 + (lane & 7);
  const uint32_t soff = srow * 32 + ((((lane >> 4) ^ (srow >> 2)) & 1) << 4);
  constexpr int NG = 1;
  uint32_t mine = 0;
  TC(0);
  #pragma unroll
  for (int hq = 0; hq < 12; hq += NG) {
    uint32_t r[NG][4];
    #pragma unroll
    for (int j = 0; j < NG; j++) {
      const int h = hq + j;
      const float qs = ct * 12 + h < 32 ? 0.25f * 1.4426950408889634f : 1.0f;
      const float f0 = rs0 * qs, f1 = rs1 * qs;
      r[j][0] = pack(acc[8 * h + 0] * f0, acc[8 * h + 1] * f0); r[j][1] = pack(acc[8 * h + 2] * f1, acc[8 * h + 3] * f1);
      r[j][2] = pack(acc[8 * h + 4] * f0, acc[8 * h + 5] * f0); r[j][3] = pack(acc[8 * h + 6] * f1, acc[8 * h + 7] * f1);
      stsm4(stg + (h >> 2) * 16384 + (h & 3) * 512 + soff, r[j][0], r[j][1], r[j][2], r[j][3]);
    }
    __syncwarp();
    #pragma unroll
    for (int j = 0; j < NG; j++) {
      const int h = hq + j;
      const uint4 v = lds128(stg + (h >> 2) * 16384 + (h & 3) * 512 + lane * 16);
      asm volatile("st.global.v4.u32 [%0], {%1, %2, %3, %4};" :: "l"((uint4*)(S->g_qkv + ((size_t)(ct * 12 + h) * 2048 + row0) * 16) + lane), "r"(v.x), "r"(v.y), "r"(v.z), "r"(v.w) : "memory");
    }
    #pragma unroll
    for (int j = 0; j < NG; j++) {
      float d0[4] = {0.f, 0.f, 0.f, 0.f}, d1[4] = {0.f, 0.f, 0.f, 0.f};
      mma16816(d0, r[j], r[j][0], r[j][2]); mma16816(d1, r[j], r[j][1], r[j][3]);
      const float mx = fmaxf(fmaxf(fmaxf(d0[0], d0[1]), fmaxf(d1[2], d1[3])), 0.f);
      const uint32_t mu = __reduce_max_sync(~0u, __float_as_uint(mx)); if (lane == hq + j) mine = mu;
    }
  }
  if (lane < 12) S->g_nrm[(ct * 12 + lane) * 128 + rt * 8 + warp] = __uint_as_float(mine);
  TC(3);
  TS(1, 4);
}

DEVI uint32_t ex2_pair(float s0, float s1) {
  const float t0 = s0 + 65662.4140625f, t1 = s1 + 65662.4140625f;
  const uint32_t y = __byte_perm(__float_as_uint(t0), __float_as_uint(t1), 0x5410);
  uint32_t m; asm("lop3.b32 %0, %1, 0x007F007F, 0x3F003F00, 0xEA;" : "=r"(m) : "r"(y));
  return hfma2(y, m, y & 0x7F807F80u);
}
constexpr uint32_t PMASK = 0x55B5;
template<bool SAFE> DEVI void exp_block(const float (&s)[32], uint32_t (&p)[4][4], float m0, float m1) {
  #pragma unroll
  for (int i = 0; i < 16; i++) {
    if (SAFE) { const float m = (i & 1) ? m1 : m0; p[i >> 2][i & 3] = pack(ex2(s[2 * i] - m), ex2(s[2 * i + 1] - m)); }
    else p[i >> 2][i & 3] = ((PMASK >> i) & 1) ? ex2_pair(s[2 * i], s[2 * i + 1]) : pack(ex2(s[2 * i]), ex2(s[2 * i + 1]));
  }
}
DEVI void addlo(uint64_t& d, uint32_t x) { uint32_t lo = (uint32_t)d + x; d = (d & 0xFFFFFFFF00000000ull) | lo; }
constexpr int AT_SMEM = 131072 + 512 + 128;

DEVI void load_q(Scratch* S, uint32_t (&qf)[4], int head, int row0, int lane) {
  const uint32_t* qp = (const uint32_t*)(S->g_qkv + ((size_t)head * S_LEN + row0) * 16) + (lane & 3);
  const int sw = ((lane >> 4) & 1) * 4;
  qf[0] = __ldcg(qp + sw); qf[1] = __ldcg(qp + 64 + sw); qf[2] = __ldcg(qp + (4 - sw)); qf[3] = __ldcg(qp + 64 + (4 - sw));
}
template<bool SAFE> DEVI void attn_body(Scratch* S, uint32_t sb, int head, int rowb, int lane, const uint32_t (&qa)[4], const uint32_t (&qb2)[4], const void* pf, int pfb) {
  const uint32_t sK = sb, sV = sb + 65536, sOnes = sb + 131072, bb = sOnes + 512;
  const uint32_t kd0 = daddr(sK) | (1u << 16);
  const uint32_t vd0 = daddr(sV) | (((sOnes - sV) >> 4) << 16);
  constexpr uint32_t VSTEP = 32u - (32u << 16);
  #pragma unroll 1
  for (int qb = 0; qb < 2; qb++) {
    const int row0 = rowb + qb * 64;
    uint32_t qf[4];
    #pragma unroll
    for (int i = 0; i < 4; i++) qf[i] = qb ? qb2[i] : qa[i];
    float o[12];
    #pragma unroll
    for (int i = 0; i < 12; i++) o[i] = 0.f;
    fence_regs(o);
    float s0[32], s1[32]; uint32_t p0[4][4], p1[4][4];
    float m0 = 0.f, m1 = 0.f;
    if (SAFE) {
      if (qb == 0) for (int i = 0; i < 8; i++) mbar_wait(bb + 8 * i, 0);
      m0 = m1 = -INFINITY;
      #pragma unroll 1
      for (int j = 0; j < 32; j++) {
        WG_FENCE();
        wg_n64_rs_z<0>(s0, qf, mkdesc(DHI32, kd0 + j * 128));
        WG_COMMIT();
        WG_WAIT(0);
        fence_regs(s0);
        #pragma unroll
        for (int i = 0; i < 8; i++) { m0 = fmaxf(m0, fmaxf(s0[4 * i], s0[4 * i + 1])); m1 = fmaxf(m1, fmaxf(s0[4 * i + 2], s0[4 * i + 3])); }
      }
      m0 = fmaxf(m0, __shfl_xor_sync(~0u, m0, 1)); m0 = fmaxf(m0, __shfl_xor_sync(~0u, m0, 2));
      m1 = fmaxf(m1, __shfl_xor_sync(~0u, m1, 1)); m1 = fmaxf(m1, __shfl_xor_sync(~0u, m1, 2));
    } else if (qb == 0) { mbar_wait(bb, 0); }
    WG_FENCE();
    wg_n64_rs_z<0>(s0, qf, mkdesc(DHI32, kd0));
    WG_COMMIT();
    WG_WAIT(0);
    if (qb == 0) { TS(2, 3); }
    uint64_t kda = mkdesc(DHI32, kd0 + 128), kdb = mkdesc(DHI32, kd0 + 256);
    uint64_t vd[8];
    #pragma unroll
    for (int i = 0; i < 8; i++) vd[i] = mkdesc(DHI32, vd0 + i * VSTEP);
    #pragma unroll 1
    for (int j = 0; j < 16; j++) {
      if (!SAFE && qb == 0 && (j & 1) && j < 15) mbar_wait(bb + 8 * ((j + 1) >> 1), 0);
      WG_FENCE();
      wg_n64_rs_z<0>(s1, qf, kda); addlo(kda, 256);
      WG_COMMIT();
      fence_regs(s0);
      exp_block<SAFE>(s0, p0, m0, m1);
      WG_FENCE();
      #pragma unroll
      for (int kk = 0; kk < 4; kk++) { wg_n24_rs_a<1>(o, p0[kk], vd[kk]); addlo(vd[kk], 8 * VSTEP); }
      WG_COMMIT();
      WG_WAIT(1);
      WG_FENCE();
      wg_n64_rs_z<0>(s0, qf, kdb); addlo(kdb, 256);
      WG_COMMIT();
      fence_regs(s1);
      exp_block<SAFE>(s1, p1, m0, m1);
      WG_FENCE();
      #pragma unroll
      for (int kk = 0; kk < 4; kk++) { wg_n24_rs_a<1>(o, p1[kk], vd[4 + kk]); addlo(vd[4 + kk], 8 * VSTEP); }
      WG_COMMIT();
      WG_WAIT(1);
    }
    WG_WAIT(0); fence_regs(o);
    const float inv0 = 1.0f / o[8], inv1 = 1.0f / o[10];
    uint2* op = (uint2*)(S->g_o + (size_t)row0 * 512 + head * 16) + (lane & 1) * 2 + ((lane >> 1) & 1);
    const bool odd = lane & 1;
    const uint32_t a0 = pack(o[0] * inv0, o[1] * inv0), b0 = pack(o[4] * inv0, o[5] * inv0), a1 = pack(o[2] * inv1, o[3] * inv1), b1 = pack(o[6] * inv1, o[7] * inv1);
    const uint32_t x0 = __shfl_xor_sync(~0u, odd ? a0 : b0, 1), x1 = __shfl_xor_sync(~0u, odd ? a1 : b1, 1);
    op[0] = odd ? make_uint2(x0, b0) : make_uint2(a0, x0);
    op[8 * 128] = odd ? make_uint2(x1, b1) : make_uint2(a1, x1);
    if (qb == 0 && pfb) l2_prefetch(pf, pfb);
  }
}

DEVI void helper_cta(Scratch* S, uint8_t* smem, int hb, const bf16* c, const bf16* wmod, const bf16* win) {
  const int tid = threadIdx.x, lane = tid & 31, warp = tid >> 5;
  float* sc = (float*)smem;
  float* red1 = sc + 512;
  float2* red = (float2*)(smem + 2048);
  for (int i = hb * 512 + tid; i < 2048 * 8; i += 2048) { S->g_st2[i] = make_float2(0.f, -1.f); S->g_st3[i] = make_float2(0.f, -1.f); }
  if (tid < 320) S->g_flag[hb * 320 + tid] = 0u;
  sc[tid] = silu_bf(c[tid]);
  __syncthreads();
  {
    const int cg = tid & 63, rg = tid >> 6;
    const bf16* wp = wmod + (size_t)rg * 64 * 3072 + 1024 + (cg >> 4) * 512 + hb * 128 + (cg & 15) * 8;
    float a[8];
    #pragma unroll
    for (int j = 0; j < 8; j++) a[j] = 0.f;
    #pragma unroll 1
    for (int b = 0; b < 4; b++) {
      uint4 w[16];
      #pragma unroll
      for (int i = 0; i < 16; i++) w[i] = __ldg((const uint4*)(wp + (size_t)(b * 16 + i) * 3072));
      #pragma unroll
      for (int i = 0; i < 16; i++) fma8(a, sc[rg * 64 + b * 16 + i], w[i]);
    }
    #pragma unroll
    for (int j = 0; j < 8; j++) red1[rg * 512 + cg * 8 + j] = a[j];
    __syncthreads();
    float v = 0.f;
    #pragma unroll
    for (int r = 0; r < 8; r++) v += red1[r * 512 + tid];
    const bf16 vb = __float2bfloat16_rn(v);
    S->g_mod[1024 + (tid >> 7) * 512 + hb * 128 + (tid & 127)] = vb;
    sc[tid] = __bfloat162float(vb);
    __syncthreads();
  }
  const int kb = lane >> 3, nb = lane & 7, kg = warp & 3;
  const int kl = kg * 32 + kb * 8, k0 = hb * 128 + kl;
  uint32_t gk[8]; float sk[8];
  #pragma unroll
  for (int i = 0; i < 8; i++) { gk[i] = pack(1.0f + sc[256 + kl + i], 1.0f + sc[256 + kl + i]); sk[i] = sc[128 + kl + i]; }
  #pragma unroll 1
  for (int gi = warp >> 2; gi < 22; gi += 4) {
    const int n = gi * 64 + nb * 8;
    float cs[8], sw[8];
    #pragma unroll
    for (int j = 0; j < 8; j++) cs[j] = sw[j] = 0.f;
    if (n < 1376) {
      uint4 w[8];
      #pragma unroll
      for (int i = 0; i < 8; i++) w[i] = __ldg((const uint4*)(win + (size_t)(k0 + i) * 1376 + n));
      uint32_t m[8][4];
      #pragma unroll
      for (int i = 0; i < 8; i++) {
        fma8(sw, sk[i], w[i]);
        m[i][0] = hmul2(w[i].x, gk[i]); m[i][1] = hmul2(w[i].y, gk[i]); m[i][2] = hmul2(w[i].z, gk[i]); m[i][3] = hmul2(w[i].w, gk[i]);
        fma8(cs, 1.0f, make_uint4(m[i][0], m[i][1], m[i][2], m[i][3]));
      }
      const int f = n >= 688 ? n - 688 : n, np = (f / 88) * 176 + (n >= 688 ? 0 : 88) + f % 88;
      #pragma unroll
      for (int j = 0; j < 8; j++) {
        const uint32_t sel = (j & 1) ? 0x7632 : 0x5410;
        *(uint4*)(S->g_wt + (size_t)(np + j) * 512 + k0) =
          make_uint4(__byte_perm(m[0][j >> 1], m[1][j >> 1], sel), __byte_perm(m[2][j >> 1], m[3][j >> 1], sel),
                     __byte_perm(m[4][j >> 1], m[5][j >> 1], sel), __byte_perm(m[6][j >> 1], m[7][j >> 1], sel));
      }
    }
    #pragma unroll
    for (int j = 0; j < 8; j++) {
      cs[j] += __shfl_xor_sync(~0u, cs[j], 8); cs[j] += __shfl_xor_sync(~0u, cs[j], 16);
      sw[j] += __shfl_xor_sync(~0u, sw[j], 8); sw[j] += __shfl_xor_sync(~0u, sw[j], 16);
    }
    if (kb == 0) {
      #pragma unroll
      for (int j = 0; j < 8; j++) red[kg * 1408 + n + j] = make_float2(cs[j], sw[j]);
    }
  }
  __syncthreads();
  for (int n = tid; n < 1376; n += 512) {
    float a = 0.f, b = 0.f;
    #pragma unroll
    for (int w = 0; w < 4; w++) { const float2 v = red[w * 1408 + n]; a += v.x; b += v.y; }
    const int f = n >= 688 ? n - 688 : n;
    S->g_cs[hb * 1408 + (f / 88) * 176 + (n >= 688 ? 0 : 88) + f % 88] = make_float2(a, b);
  }
  TS(7, 3);
  pdl_wait();
  pdl_trigger();
  S->g_st1[hb * 512 + tid] = 0ull;
  if (hb == 0) S->g_modx[tid] = 0ull;
}

__global__ void __cluster_dims__(2, 1, 1) __launch_bounds__(512, 1)
k2_attn(Scratch* __restrict__ S, const bf16* __restrict__ c, const bf16* __restrict__ wmod, const bf16* __restrict__ win,
        const bf16* __restrict__ wo, const bf16* __restrict__ wsp, const bf16* __restrict__ wout) {
  extern __shared__ __align__(1024) uint8_t smem[];
  if (blockIdx.x < 4) { TS(7, 0); helper_cta(S, smem, blockIdx.x, c, wmod, win); TS(7, 4); return; }
  const uint32_t sb = smem_u32(smem);
  const uint32_t sK = sb, sV = sb + 65536, bb = sb + 131072 + 512;
  const int bid = blockIdx.x - 4;
  TS(2, 0);
  const int head = bid >> 2, qq = bid & 3;
  const uint32_t rank = bid & 1;
  const int tid = threadIdx.x, wg = tid >> 7, warp = (tid >> 5) & 3, lane = tid & 31;
  if (tid == 0) { for (int i = 0; i < 8; i++) { mbar_init(bb + 8 * i, 1); } fence_bar_init(); for (int i = 0; i < 8; i++) mbar_expect(bb + 8 * i, 16384); }
  if (tid < 128) ((uint32_t*)(smem + 131072))[tid] = 0x3F803F80u;
  asm volatile("fence.proxy.async.shared::cta;" ::: "memory");
  __syncthreads();
  cluster_sync();
  const int rowb = qq * 512 + wg * 128 + warp * 16 + (lane >> 2);
  const uint8_t* src = (const uint8_t*)(S->g_qkv + (size_t)(32 + 32 * rank + head) * S_LEN * 16) + (tid >> 6) * 8192;
  const uint32_t dst = (rank ? sV : sK) + (tid >> 6) * 8192;
  TS(2, 1);
  pdl_wait();
  TS(2, 2);
  if (tid == 0) bulk_g2s_mc(dst, src, 8192, bb);
  uint32_t qa[4], qb[4];
  load_q(S, qa, head, rowb, lane); load_q(S, qb, head, rowb + 64, lane);
  volatile uint32_t* sflag = (volatile uint32_t*)(smem + 131072 + 512 + 64);
  if (tid >= 480) {
    const float4 nk = __ldcg((const float4*)(S->g_nrm + (32 + head) * 128) + lane);
    const float4 nv = __ldcg((const float4*)(S->g_nrm + (64 + head) * 128) + lane);
    const float nq = __ldcg(S->g_nrm + head * 128 + qq * 32 + lane);
    const float mk = __uint_as_float(__reduce_max_sync(~0u, __float_as_uint(fmaxf(fmaxf(nk.x, nk.y), fmaxf(nk.z, nk.w)))));
    const float mv = __uint_as_float(__reduce_max_sync(~0u, __float_as_uint(fmaxf(fmaxf(nv.x, nv.y), fmaxf(nv.z, nv.w)))));
    const float mq = __uint_as_float(__reduce_max_sync(~0u, __float_as_uint(nq)));
    if (lane == 0) *sflag = (mq * mk <= 3600.f && mv <= 1e30f) ? 1u : 0u;
  }
  pdl_trigger();
  const bool any = __syncthreads_or((qa[0] & qa[1] & qa[2] & qa[3] & qb[0] & qb[1] & qb[2] & qb[3]) == 0xFFFFFFFFu);
  if ((tid & 63) == 0 && tid) bulk_g2s_mc(dst, src, 8192, bb + 8 * (tid >> 6) + (any ? 0 : 0));
  const uint8_t* pf = tid < 4 ? (const uint8_t*)wsp + (bid * 4 + tid) * 16384 : (tid == 4 ? (const uint8_t*)wout + bid * 5504 : (const uint8_t*)wo + bid * 4096);
  const int pfb = tid < 4 ? 16384 : (tid == 4 ? 5504 : (tid == 5 ? 4096 : 0));
  if (*sflag) attn_body<false>(S, sb, head, rowb, lane, qa, qb, pf, pfb);
  else attn_body<true>(S, sb, head, rowb, lane, qa, qb, pf, pfb);
  TS(2, 4);
}

constexpr int F_RB = 131072, F_SB = 11264, F_BAR = F_RB + 8 * F_SB, F_CS = F_BAR + 256, F_SMEM = F_CS + 1408;
constexpr int F_PRE = 3;
struct FMaps { CUtensorMap o, wo, x1, wr, wt, wsp, z2, u, wout; };
DEVI uint32_t gelu2(float a, float b) {
  const float ta = tanh_fast(a * fmaf(a * a, 0.7978845608f * 0.044715f, 0.7978845608f));
  const float tb = tanh_fast(b * fmaf(b * b, 0.7978845608f * 0.044715f, 0.7978845608f));
  const float ha = 0.5f * a, hb = 0.5f * b;
  return pack(fmaf(ha, ta, ha), fmaf(hb, tb, hb));
}
DEVI void tma_store(const CUtensorMap* tm, uint32_t src, int c0, int c1) {
  asm volatile("cp.async.bulk.tensor.2d.global.shared::cta.bulk_group [%0, {%2, %3}], [%1];\n"
               "cp.async.bulk.commit_group;\ncp.async.bulk.wait_group 0;\nfence.proxy.async.global;"
               :: "l"(tm), "r"(src), "r"(c0), "r"(c1) : "memory");
}
DEVI void flag_add(uint32_t* f, uint32_t v = 1) { asm volatile("red.relaxed.gpu.global.add.u32 [%0], %1;" :: "l"(f), "r"(v) : "memory"); }
DEVI uint32_t flag_ld(const uint32_t* f) { uint32_t v; asm volatile("ld.acquire.gpu.global.u32 %0, [%1];" : "=r"(v) : "l"(f) : "memory"); return v; }
DEVI void flag_wait(const uint32_t* f, uint32_t n) {
  int guard = 0;
  while (flag_ld(f) < n) if (++guard > (1 << 20)) __trap();
  asm volatile("fence.proxy.async.global;" ::: "memory");
}
DEVI void peer_copy(uint32_t dst, uint32_t src, int bytes, uint32_t bar, uint32_t rank) {
  asm volatile("{\n.reg .b32 rd, rb;\nmapa.shared::cluster.u32 rd, %0, %4;\nmapa.shared::cluster.u32 rb, %3, %4;\n"
               "cp.async.bulk.shared::cluster.shared::cta.mbarrier::complete_tx::bytes [rd], [%1], %2, [rb];\n}"
               :: "r"(dst), "r"(src), "r"(bytes), "r"(bar), "r"(rank) : "memory");
}
DEVI void bits_wait(const uint32_t* f, uint32_t& have, uint32_t need) {
  if ((have & need) == need) return;
  int guard = 0;
  do { have = flag_ld(f); if (++guard > (1 << 20)) __trap(); } while ((have & need) != need);
  asm volatile("fence.proxy.async.global;" ::: "memory");
}
DEVI void fence_async_smem() { asm volatile("fence.proxy.async.shared::cta;" ::: "memory"); }
template<int N> DEVI void mma_stage(float (&acc)[N], uint32_t ad, uint32_t bd) {
  #pragma unroll
  for (int kk = 0; kk < 4; kk++) {
    if constexpr (N == 44) wg_n88_ss_a<0, 0>(acc, mkdesc(DHI128, ad + kk * 2), mkdesc(DHI128, bd + kk * 2));
    else wg_n64_ss_a<0, 1>(acc, mkdesc(DHI128, ad + kk * 2), mkdesc(DHI128, bd + kk * 128));
  }
}
template<int N, bool BL, bool FIN = true> DEVI void mma_loop(float (&acc)[N], uint32_t barF, uint32_t ad0, uint32_t bd0, int bst, int use, int s0, int s1, int rel, int lane) {
  #pragma unroll 1
  for (int s = s0; s < s1; s++) {
    mbar_wait(barF + 8 * (s & 7), (use + (s >> 3)) & 1);
    WG_FENCE();
    mma_stage(acc, ad0 + (s & 7) * 1024, bd0 + (BL ? s : (s & 7)) * bst);
    WG_COMMIT();
    WG_WAIT(1);
    if (s >= 1 && s - 1 < rel && lane < 2) mbar_arrive_rank(barF + 64 + 8 * ((s - 1) & 7), lane);
  }
  if (!FIN) return;
  WG_WAIT(0);
  fence_regs(acc);
  if (s1 - 1 < rel && lane < 2) mbar_arrive_rank(barF + 64 + 8 * ((s1 - 1) & 7), lane);
}
template<int N> DEVI void zero_acc(float (&a)[N]) {
  #pragma unroll
  for (int i = 0; i < N; i++) a[i] = 0.f;
  fence_regs(a);
}
DEVI void quad_sum(float& s0, float& q0, float& s1, float& q1) {
  #pragma unroll
  for (int o = 1; o < 4; o <<= 1) {
    s0 += __shfl_xor_sync(~0u, s0, o); q0 += __shfl_xor_sync(~0u, q0, o);
    s1 += __shfl_xor_sync(~0u, s1, o); q1 += __shfl_xor_sync(~0u, q1, o);
  }
}
DEVI void gate_res(const float (&acc)[32], uint32_t gw, uint4 (&res)[4], uint32_t stg, int lane) {
  const int srow = ((lane >> 3) & 1) * 8 + (lane & 7), t = lane & 3;
  #pragma unroll
  for (int p = 0; p < 4; p++) {
    uint32_t r[4];
    const uint32_t gv[2] = {__shfl_sync(~0u, gw, p * 8 + t), __shfl_sync(~0u, gw, p * 8 + 4 + t)};
    #pragma unroll
    for (int i = 0; i < 4; i++) r[i] = hmul2(gv[i >> 1], pack(acc[8 * p + 2 * i], acc[8 * p + 2 * i + 1]));
    stsm4(stg + srow * 128 + (((p * 2 + (lane >> 4)) ^ (lane & 7)) << 4), r[0], r[1], r[2], r[3]);
  }
  __syncwarp();
  #pragma unroll
  for (int i = 0; i < 4; i++) {
    const int r = i * 4 + (lane >> 3);
    const uint4 v = lds128(stg + r * 128 + (((lane & 7) ^ (r & 7)) << 4));
    res[i].x = hadd2(res[i].x, v.x); res[i].y = hadd2(res[i].y, v.y); res[i].z = hadd2(res[i].z, v.z); res[i].w = hadd2(res[i].w, v.w);
  }
}

__global__ void __cluster_dims__(2, 1, 1) __launch_bounds__(384, 1)
k3_chain(const __grid_constant__ FMaps M, Scratch* __restrict__ S, const bf16* __restrict__ x, const bf16* __restrict__ bsp, bf16* __restrict__ out) {
  TS(3, 0);
  extern __shared__ __align__(1024) uint8_t smem[];
  const uint32_t sb = smem_u32(smem);
  const uint32_t barF = sb + F_BAR, barE = barF + 64, barW = barF + 128, sB = sb + F_RB;
  const int tid = threadIdx.x, lane = tid & 31, warp = tid >> 5;
  const uint32_t rank = blockIdx.x & 1;
  const int ct = blockIdx.x & 7, rt = blockIdx.x >> 3;
  uint32_t* fx = S->g_flag + rt * 32; uint32_t* fu = fx + 512; uint32_t* fz = S->g_flag + 1024 + ct * 32;
  if (tid == 0) {
    for (int i = 0; i < 8; i++) { mbar_init(barF + 8 * i, 1); mbar_init(barE + 8 * i, 16); }
    mbar_init(barW, 1);
    fence_bar_init();
  }
  cluster_sync();
  auto kx = [&](int s) { return s < 2 ? ct ^ s : (s - 2 < (ct & 6) ? s - 2 : s); };
  if (warp == 8) {
    auto ldA = [&](const CUtensorMap* tm, int sl, int kc) { tma2d_mc(sb + sl * 16384 + rank * 8192, tm, barF + 8 * sl, kc * 64, rt * 128 + rank * 64); };
    if (lane == 0) {
      pdl_wait();
      for (int s = 0; s < 8; s++) ldA(&M.o, s, s);
      for (int s = 0; s < 8; s++) mbar_wait(barE + 8 * s, 0);
      uint32_t have = 0;
      for (int s = 2; s < 8; s++) { bits_wait(fx, have, 1u << (2 * kx(s) + rank)); ldA(&M.x1, s, kx(s)); }
      for (int s = 0; s < 8; s++) mbar_wait(barE + 8 * s, 1);
      #pragma unroll 1
      for (int i = 0; i < 32; i++) { mbar_wait(barE + 8 * (i & 7), (i >> 3) & 1); ldA(&M.wsp, i & 7, i < 2 ? 2 * rt + i : (i - 2 < 2 * rt ? i - 2 : i)); }
      for (int s = 0; s < 8; s++) mbar_wait(barE + 8 * s, 0);
      have = 0;
      TA(0);
      for (int s = 2; s < 8; s++) { bits_wait(fu, have, (s < 7 ? 1u << 2 * kx(s) : (1u << 2 * kx(s)) | (0x50000u << (ct & 6) * 2)) << rank); ldA(&M.u, s, kx(s)); }
      TA(3);
    }
    return;
  }
  if (warp == 11) {
    if (lane == 0) {
      for (int s = 0; s < 8; s++) { mbar_expect(barF + 8 * s, 24576); if (s < F_PRE) tma2d(sB + s * F_SB, &M.wo, barF + 8 * s, ct * 64, s * 64); }
      pdl_wait();
      for (int s = F_PRE; s < 8; s++) tma2d(sB + s * F_SB, &M.wo, barF + 8 * s, ct * 64, s * 64);
      for (int s = 0; s < 8; s++) { mbar_wait(barE + 8 * s, 0); mbar_expect(barF + 8 * s, s ? 16384 + F_SB : F_SB); tma2d(sB + s * F_SB, &M.wt, barF + 8 * s, kx(s) * 64, ct * 176); }
      for (int s = 0; s < 8; s++) { mbar_wait(barE + 8 * s, 1); mbar_expect(barF + 8 * s, F_SB); tma2d(sB + s * F_SB, &M.wt, barF + 8 * s, kx(s) * 64, ct * 176 + 88); }
      uint32_t have = 0;
      mbar_wait(barE, 0); mbar_wait(barE + 8, 0);
      #pragma unroll 1
      for (int i = 2; i < 32; i++) {
        const int kc = i - 2 < 2 * rt ? i - 2 : i, sl = i & 7;
        bits_wait(fz, have, (1u << kc) | (i >= 8 ? 3u << (2 * rt) : 0u));
        mbar_wait(barE + 8 * sl, (i >> 3) & 1); mbar_expect(barF + 8 * sl, 16384 + F_SB);
        tma2d(sB + sl * F_SB, &M.z2, barF + 8 * sl, kc * 64, ct * 88);
      }
      mbar_expect(barW, 9 * 8192);
      #pragma unroll
      for (int s = 0; s < 8; s++) {
        mbar_wait(barE + 8 * s, 0); mbar_expect(barF + 8 * s, s == 0 ? 8192 : s == 1 ? 24576 : 16384);
        #pragma unroll
        for (int j = s * 11 / 8; j < (s + 1) * 11 / 8 && j < 8; j++) tma2d(sB + j * 8192, &M.wout, s < 2 ? barF + 8 * s : barW, ct * 64, kx(j) * 88);
        if (s >= 6) for (int j = 4 * s - 24; j < 4 * s - 20; j++) tma2d(sB + 65536 + j * 3072, &M.wr, barW, ct * 64, j * 88 + 64);
      }
      TA(6);
      have = 0;
      bits_wait(fu, have, 0x55555555u << rank);
      TA(1);
      for (int s = 0; s < 3; s++) { mbar_wait(barE + 8 * s, 1); mbar_expect(barF + 8 * s, 16384); bulk_g2s_mc(sb + s * 16384 + rank * 8192, S->g_ul + ((rt * 2 + rank) * 24 + s * 8) * 512, 8192, barF + 8 * s); }
    }
    return;
  }
  if (warp > 8) {
    if (tid < 297) tmap_prefetch(&M.o + lane);
    const int h = warp - 9;
    pdl_wait();
    mbar_wait(barF + 32, 0);
    float4 cv[2][4];
    #pragma unroll
    for (int k = 0; k < 2; k++)
      #pragma unroll
      for (int i = 0; i < 4; i++) cv[k][i] = __ldcg((const float4*)(S->g_cs + i * 1408 + ct * 176) + min(tid - 288 + k * 64, 87));
    bar_sync(6 + h, 160);
    if (lane == 0) {
      tma_store(&M.x1, sb + h * 8192, ct * 64, rt * 128 + h * 64); flag_add(fx, 1u << (2 * ct + h));
      mbar_wait(barE + 8, 0); peer_copy(sb + 16384 + h * 8192, sb + h * 8192, 8192, barF + 8, rank ^ 1);
    }
    __syncwarp();
    #pragma unroll
    for (int k = 0; k < 2; k++)
      *(float4*)(smem + F_CS + min(tid - 288 + k * 64, 87) * 16) = make_float4(cv[k][0].x + cv[k][1].x + cv[k][2].x + cv[k][3].x, cv[k][0].y + cv[k][1].y + cv[k][2].y + cv[k][3].y,
                                                                              cv[k][0].z + cv[k][1].z + cv[k][2].z + cv[k][3].z, cv[k][0].w + cv[k][1].w + cv[k][2].w + cv[k][3].w);
    bar_arrive(1, 320);
    bar_sync(2 + h, 160);
    if (lane == 0) { mbar_expect(barF + 8 * h, 16384); tma_store(&M.z2, sB + h * F_SB, rt * 128 + h * 64, ct * 88); flag_add(fz, 1u << (2 * rt + h)); }
    __syncwarp();
    bar_sync(8 + h, 160);
    if (lane == 0) {
      TM(7);
      asm volatile("cp.async.bulk.tensor.2d.global.shared::cta.bulk_group [%0, {%2, %3}], [%1];\ncp.async.bulk.commit_group;\n"
                   "cp.async.bulk.global.shared::cta.bulk_group [%4], [%5], 3072;\ncp.async.bulk.commit_group;\ncp.async.bulk.wait_group 1;\nfence.proxy.async.global;"
                   :: "l"(&M.u), "r"(sb + h * 8192), "r"(ct * 64), "r"(rt * 128 + h * 64), "l"(S->g_ul + ((rt * 2 + h) * 24 + ct * 3) * 512), "r"(sb + 7 * 16384 + h * 8192) : "memory");
      flag_add(fu, 1u << (2 * ct + h));
      mbar_wait(barE + 8, 0); peer_copy(sb + 16384 + h * 8192, sb + h * 8192, 8192, barF + 8, rank ^ 1);
      TM(4);
      asm volatile("cp.async.bulk.wait_group 0;\nfence.proxy.async.global;" ::: "memory");
      flag_add(fu, 0x10000u << (2 * ct + h));
      TM(2);
    }
    return;
  }
  const int g = lane >> 2, t = lane & 3, wg = warp >> 2;
  const int row0 = rt * 128 + warp * 16;
  uint4 res[4];
  #pragma unroll
  for (int i = 0; i < 4; i++) res[i] = __ldg((const uint4*)(x + (size_t)(row0 + i * 4 + (lane >> 3)) * 512 + ct * 64) + (lane & 7));
  const uint32_t bs0 = __bfloat16_as_ushort(bsp[row0 + g]) * 0x10001u, bs1 = __bfloat16_as_ushort(bsp[row0 + g + 8]) * 0x10001u;
  const uint32_t ad0 = daddr(sb + wg * 8192) | (1u << 16), bdK = daddr(sB) | (1u << 16), bdT = daddr(sB) | ((8192u >> 4) << 16);
  TS(3, 1);
  pdl_wait();
  TS(3, 2);
  mbar_wait(barF, 0);
  const uint32_t ga = __ldcg((const uint32_t*)(S->g_mod + 1024 + ct * 64) + lane), gb = __ldcg((const uint32_t*)(S->g_mod + 2560 + ct * 64) + lane);
  {
    float acc[32];
    zero_acc(acc);
    mma_loop<32, false>(acc, barF, ad0, bdT, F_SB / 16, 0, 0, 8, 8, lane);
    TS(3, 3);
    const uint32_t stg = sb + warp * 2048;
    gate_res(acc, ga, res, stg, lane);
    #pragma unroll
    for (int i = 0; i < 4; i++) { const int r = i * 4 + (lane >> 3); sts128(stg + r * 128 + (((lane & 7) ^ (r & 7)) << 4), res[i]); }
    fence_async_smem();
    bar_sync(6 + wg, 160);
    TS(3, 4);
  }
  float acc[44], ac1[44];
  uint32_t z1[22];
  zero_acc(acc); zero_acc(ac1);
  mbar_wait(barF, 1); WG_FENCE(); mma_stage(acc, ad0, bdK); WG_COMMIT();
  {
    float so = 0.f, qo = 0.f;
    #pragma unroll
    for (int i = 0; i < 4; i++) {
      float s = 0.f, q = 0.f;
      const uint32_t w[4] = {res[i].x, res[i].y, res[i].z, res[i].w};
      #pragma unroll
      for (int j = 0; j < 4; j++) { const float a = blo(w[j]), b = bhi(w[j]); s += a + b; q = fmaf(a, a, fmaf(b, b, q)); }
      #pragma unroll
      for (int o = 1; o < 8; o <<= 1) { s += __shfl_xor_sync(~0u, s, o); q += __shfl_xor_sync(~0u, q, o); }
      if ((lane & 7) == i) { so = s; qo = q; }
    }
    if ((lane & 7) < 4) asm volatile("{\n.reg .b64 v;\nmov.b64 v, {%1, %2};\nst.relaxed.gpu.global.b64 [%0], v;\n}" :: "l"(S->g_st2 + ct * 2048 + row0 + (lane & 7) * 4 + (lane >> 3)), "f"(so), "f"(qo) : "memory");
  }
  mma_loop<44, false, false>(acc, barF, ad0, bdK, F_SB / 16, 1, 1, 2, 8, lane);
  bar_sync(1, 320);
  mbar_wait(barF + 16, 1);
  TS(4, 2);
  const float2* sp = S->g_st2 + t * 4096 + row0 + g;
  float2 u0, u1, u2, u3;
  auto ld_st = [&]() {
    asm volatile("{\n.reg .b64 a, b, c, d;\nld.relaxed.gpu.global.b64 a, [%8];\nld.relaxed.gpu.global.b64 b, [%8 + 64];\n"
                 "ld.relaxed.gpu.global.b64 c, [%8 + 16384];\nld.relaxed.gpu.global.b64 d, [%8 + 16448];\n"
                 "mov.b64 {%0, %1}, a;\nmov.b64 {%2, %3}, b;\nmov.b64 {%4, %5}, c;\nmov.b64 {%6, %7}, d;\n}"
                 : "=f"(u0.x), "=f"(u0.y), "=f"(u1.x), "=f"(u1.y), "=f"(u2.x), "=f"(u2.y), "=f"(u3.x), "=f"(u3.y) : "l"(sp) : "memory");
  };
  ld_st();
  mma_loop<44, false, false>(acc, barF, ad0, bdK, F_SB / 16, 1, 2, 7, 8, lane);
  #pragma unroll 1
  for (int guard = 0; guard < (1 << 20); guard++) {
    if (u0.y != -1.f && u1.y != -1.f && u2.y != -1.f && u3.y != -1.f) break;
    ld_st();
  }
  __syncwarp();
  uint32_t nm0, nm1, sd0, sd1; float rs0, rs1;
  {
    float s0 = u0.x + u2.x, q0 = u0.y + u2.y, s1 = u1.x + u3.x, q1 = u1.y + u3.y;
    quad_sum(s0, q0, s1, q1);
    ln_params(s0, q0, 1.f / 512, nm0, sd0, rs0);
    ln_params(s1, q1, 1.f / 512, nm1, sd1, rs1);
  }
  const float m0 = blo(nm0), m1 = blo(nm1);
  auto act = [&](const float (&a)[44], uint32_t (&z)[22], int j, int jo) {
    const uint4 cv = lds128(sb + F_CS + (j + jo) * 64 + t * 16);
    const float ca = __uint_as_float(cv.x), wa = __uint_as_float(cv.y), cb = __uint_as_float(cv.z), wb = __uint_as_float(cv.w);
    z[2 * j] = gelu2(fmaf(fmaf(m0, ca, a[4 * j]), rs0, wa), fmaf(fmaf(m0, cb, a[4 * j + 1]), rs0, wb));
    z[2 * j + 1] = gelu2(fmaf(fmaf(m1, ca, a[4 * j + 2]), rs1, wa), fmaf(fmaf(m1, cb, a[4 * j + 3]), rs1, wb));
  };
  mma_loop<44, false>(acc, barF, ad0, bdK, F_SB / 16, 1, 7, 8, 8, lane);
  TS(4, 3);
  auto z1_stage = [&](int s) {
    mbar_wait(barF + 8 * s, 0); WG_FENCE(); mma_stage(ac1, ad0 + s * 1024, bdK + s * (F_SB / 16)); WG_COMMIT();
    if (s) { WG_WAIT(1); if (lane < 2) mbar_arrive_rank(barE + 8 * (s - 1), lane); }
  };
  {
    uint32_t z[22];
    unsigned long long* st = (unsigned long long*)(S->g_st3 + (size_t)(row0 + g) * 8);
    float s0 = 0.f, q0 = 0.f, s1 = 0.f, q1 = 0.f;
    #pragma unroll
    for (int j = 0; j < 11; j++) {
      act(acc, z, j, 0);
      float a = blo(z[2 * j]), b = bhi(z[2 * j]); s0 += a + b; q0 = fmaf(a, a, fmaf(b, b, q0));
      a = blo(z[2 * j + 1]); b = bhi(z[2 * j + 1]); s1 += a + b; q1 = fmaf(a, a, fmaf(b, b, q1));
    }
    quad_sum(s0, q0, s1, q1);
    if (t < 2) {
      const unsigned long long v = t ? (((unsigned long long)__float_as_uint(q1) << 32) | __float_as_uint(s1)) : (((unsigned long long)__float_as_uint(q0) << 32) | __float_as_uint(s0));
      asm volatile("st.relaxed.gpu.global.u64 [%0], %1;" :: "l"(st + t * 64 + ct), "l"(v) : "memory");
    }
    TS(4, 5);
    unsigned long long v[4];
    auto poll = [&]() {
      #pragma unroll
      for (int i = 0; i < 4; i++) asm volatile("ld.relaxed.gpu.global.u64 %0, [%1];" : "=l"(v[i]) : "l"(st + (i >> 1) * 64 + t * 2 + (i & 1)) : "memory");
    };
    z1_stage(0); z1_stage(1);
    poll();
    z1_stage(2);
    TS(4, 7);
    #pragma unroll 1
    for (int guard = 0; guard < (1 << 20); guard++) {
      bool ok = true;
      #pragma unroll
      for (int i = 0; i < 4; i++) ok = ok && (uint32_t)(v[i] >> 32) != 0xBF800000u;
      if (ok) break;
      poll();
    }
    __syncwarp();
    s0 = __uint_as_float((uint32_t)v[0]) + __uint_as_float((uint32_t)v[1]); q0 = __uint_as_float((uint32_t)(v[0] >> 32)) + __uint_as_float((uint32_t)(v[1] >> 32));
    s1 = __uint_as_float((uint32_t)v[2]) + __uint_as_float((uint32_t)v[3]); q1 = __uint_as_float((uint32_t)(v[2] >> 32)) + __uint_as_float((uint32_t)(v[3] >> 32));
    quad_sum(s0, q0, s1, q1);
    uint32_t zm0, zm1; float zr0, zr1;
    ln_params(s0, q0, 1.f / 688, zm0, sd0, zr0);
    ln_params(s1, q1, 1.f / 688, zm1, sd1, zr1);
    TS(4, 6);
    mbar_wait(barE + 8 * wg, 0);
    const int mi = lane >> 3;
    const uint32_t pc = (warp & 3) * 2 + (mi & 1);
    #pragma unroll
    for (int p = 0; p < 6; p++) {
      uint32_t r[4];
      #pragma unroll
      for (int i = 0; i < 4; i++) if (4 * p + i < 22) {
        const uint32_t d = hadd2(z[4 * p + i], (i & 1) ? zm1 : zm0);
        const float rs = (i & 1) ? zr1 : zr0;
        r[i] = pack(blo(d) * rs, bhi(d) * rs);
      }
      const uint32_t a = sB + wg * F_SB + (p * 16 + (mi >> 1) * 8 + (lane & 7)) * 128 + ((pc ^ (lane & 7)) << 4);
      if (p < 5) stsm4t(a, r[0], r[1], r[2], r[3]); else stsm2t(a, r[0], r[1]);
    }
    fence_async_smem();
    bar_arrive(2 + wg, 160);
    TS(4, 4);
  }
  mma_loop<44, false>(ac1, barF, ad0, bdK, F_SB / 16, 2, 3, 8, 8, lane);
  zero_acc(acc);
  TS(5, 2);
  #pragma unroll
  for (int s = 0; s < 11; s++) {
    mbar_wait(barF + 8 * (s & 7), (3 + (s >> 3)) & 1);
    WG_FENCE();
    mma_stage(acc, ad0 + (s & 7) * 1024, bdK + (s & 7) * (F_SB / 16));
    WG_COMMIT();
    act(ac1, z1, s, 11);
    if (s) { WG_WAIT(1); if (lane < 2) mbar_arrive_rank(barE + 8 * ((s - 1) & 7), lane); }
  }
  mma_loop<44, false>(acc, barF, ad0, bdK, F_SB / 16, 3, 11, 32, 32, lane);
  TS(5, 3);
  {
    #pragma unroll
    for (int p = 0; p < 6; p++) {
      uint32_t r[4];
      #pragma unroll
      for (int i = 0; i < 4; i++) if (4 * p + i < 22) r[i] = hmul2(z1[4 * p + i], hadd2(pack(acc[8 * p + 2 * i], acc[8 * p + 2 * i + 1]), (i & 1) ? bs1 : bs0));
      if (p == 4) bar_sync(4 + wg, 128);
      const uint32_t a = p < 4 ? sb + (warp * 16 + (lane & 15)) * 128 + (((2 * p + (lane >> 4)) ^ (lane & 7)) << 4)
                               : sb + 7 * 16384 + wg * 8192 + ((p - 4) * 2 + (lane >> 4)) * 1024 + (warp & 3) * 256 + (lane & 15) * 16;
      if (p < 5) stsm4(a, r[0], r[1], r[2], r[3]); else stsm2(a, r[0], r[1]);
    }
    fence_async_smem();
    bar_sync(8 + wg, 160);
  }
  TS(5, 4);
  {
    float ac[32];
    zero_acc(ac);
    mma_loop<32, true, false>(ac, barF, ad0, bdT, 512, 7, 0, 2, 3, lane);
    mbar_wait(barW, 0);
    mbar_wait(barF + 16, 1); if (tid == 0) TA(5);
    mma_loop<32, true, false>(ac, barF, ad0, bdT, 512, 7, 2, 8, 3, lane);
    #pragma unroll 1
    for (int s = 0; s < 3; s++) {
      mbar_wait(barF + 8 * s, 0);
      WG_FENCE();
      #pragma unroll
      for (int kk = 0; kk < 4; kk++) wg_n64_ss_a<0, 1>(ac, mkdesc(128 >> 4, (daddr(sb + wg * 8192) | (64u << 16)) + s * 1024 + kk * 128), mkdesc(DHI128, bdT + (8 + s) * 512 + kk * 128));
      WG_COMMIT();
    }
    WG_WAIT(0);
    fence_regs(ac);
    TS(6, 3);
    gate_res(ac, gb, res, sb + 3 * 16384 + warp * 2048, lane);
    #pragma unroll
    for (int i = 0; i < 4; i++) *((uint4*)(out + (size_t)(row0 + i * 4 + (lane >> 3)) * 512 + ct * 64) + (lane & 7)) = res[i];
  }
  TS(6, 4);
}

typedef CUresult (*EncFn)(CUtensorMap*, CUtensorMapDataType, cuuint32_t, void*, const cuuint64_t*, const cuuint64_t*,
                          const cuuint32_t*, const cuuint32_t*, CUtensorMapInterleave, CUtensorMapSwizzle,
                          CUtensorMapL2promotion, CUtensorMapFloatOOBfill);
static CUtensorMap make_map(EncFn fn, const void* p, int rows, int cols, int box_rows, int box_cols = 64) {
  CUtensorMap tm;
  cuuint64_t gd[2] = {(cuuint64_t)cols, (cuuint64_t)rows}, gs[1] = {(cuuint64_t)cols * 2};
  cuuint32_t bx[2] = {(cuuint32_t)box_cols, (cuuint32_t)box_rows}, es[2] = {1, 1};
  fn(&tm, CU_TENSOR_MAP_DATA_TYPE_BFLOAT16, 2, (void*)p, gd, gs, bx, es, CU_TENSOR_MAP_INTERLEAVE_NONE,
     box_cols == 64 ? CU_TENSOR_MAP_SWIZZLE_128B : CU_TENSOR_MAP_SWIZZLE_NONE, CU_TENSOR_MAP_L2_PROMOTION_L2_256B, CU_TENSOR_MAP_FLOAT_OOB_FILL_NONE);
  return tm;
}
template<typename... KA, typename... A>
static void launch(void (*k)(KA...), int grid, int block, int smem, bool pdl, A... args) {
  cudaLaunchConfig_t cfg = {};
  cfg.gridDim = dim3(grid); cfg.blockDim = dim3(block); cfg.dynamicSmemBytes = smem; cfg.stream = cudaStreamPerThread;
  cudaLaunchAttribute at[1];
  at[0].id = cudaLaunchAttributeProgrammaticStreamSerialization; at[0].val.programmaticStreamSerializationAllowed = 1;
  cfg.attrs = at; cfg.numAttrs = pdl ? 1 : 0;
  cudaLaunchKernelEx(&cfg, k, args...);
}

extern "C" void kernel_launch(void* const* d_in, const int* in_sizes, int n_in, void* d_out, int out_size) {
  const bf16* x = (const bf16*)d_in[0]; const bf16* wqkv = (const bf16*)d_in[1]; const bf16* wo = (const bf16*)d_in[2];
  const bf16* win = (const bf16*)d_in[4]; const bf16* wsp = (const bf16*)d_in[5]; const bf16* bsp = (const bf16*)d_in[6];
  const bf16* wout = (const bf16*)d_in[7]; const bf16* c = (const bf16*)d_in[8]; const bf16* wmod = (const bf16*)d_in[9];
  void* fnp = nullptr; cudaDriverEntryPointQueryResult qr;
  cudaGetDriverEntryPoint("cuTensorMapEncodeTiled", &fnp, cudaEnableDefault, &qr);
  EncFn fn = (EncFn)fnp;
  Scratch* S = nullptr;
  cudaGetSymbolAddress((void**)&S, g_scratch);
  void *po = S->g_o, *px1 = S->g_x1, *pz2 = S->g_z2t, *pu = S->g_u, *pwt = S->g_wt;
  const CUtensorMap tmX = make_map(fn, x, 2048, 512, 128), tmWqkv = make_map(fn, wqkv, 512, 1536, 64);
  FMaps M;
  M.o = make_map(fn, po, 2048, 512, 64); M.wo = make_map(fn, wo, 512, 512, 64);
  M.x1 = make_map(fn, px1, 2048, 512, 64); M.wr = make_map(fn, wout, 688, 512, 24); M.wt = make_map(fn, pwt, 1408, 512, 88);
  M.wsp = make_map(fn, wsp, 2048, 2048, 64); M.z2 = make_map(fn, pz2, 688, 2048, 88);
  M.u = make_map(fn, pu, 2048, 512, 64); M.wout = make_map(fn, wout, 688, 512, 64);
  cudaFuncSetAttribute(k1_qkv, cudaFuncAttributeMaxDynamicSharedMemorySize, T1_SMEM);
  cudaFuncSetAttribute(k2_attn, cudaFuncAttributeMaxDynamicSharedMemorySize, AT_SMEM);
  cudaFuncSetAttribute(k3_chain, cudaFuncAttributeMaxDynamicSharedMemorySize, F_SMEM);
  launch(k1_qkv, 128, 384, T1_SMEM, false, tmX, tmWqkv, S, x, c, wmod, wqkv);
  launch(k2_attn, 132, 512, AT_SMEM, true, S, c, wmod, win, wo, wsp, wout);
  launch(k3_chain, 128, 384, F_SMEM, true, M, S, x, bsp, (bf16*)d_out);
}
```
